```python
import torch

def _softmax(x, axis=-1):
    return torch.softmax(x, dim=axis)
def _gelu(x):
    return torch.nn.functional.gelu(x, approximate="tanh")
def _silu(x):
    return torch.nn.functional.silu(x)
def _sigmoid(x):
    return torch.sigmoid(x)
def _layernorm(x, axis=-1, eps=1e-5):
    m = x.mean(dim=axis, keepdim=True)
    v = x.var(dim=axis, keepdim=True, unbiased=False)
    return (x - m) / torch.sqrt(v + eps)
def _scatter_add(tgt, idx, src, axis=0):
    return tgt.clone().index_add_(axis, idx, src)
def _segment_sum(src, seg, n):
    out = torch.zeros((n,) + src.shape[1:], dtype=src.dtype)
    return out.index_add_(0, seg, src)
def _pad(x, pw):
    flat = tuple(v for pair in reversed(pw) for v in pair)
    return torch.nn.functional.pad(x, flat)

kernel_name = 'gated_mix__linear_attn_block__glu_gated_reglu__prompt'

def setup_inputs():

    _w = (lambda a: (lambda t: t.to(torch.bfloat16) if t.is_floating_point() else t)(torch.as_tensor(a)))
    def _A_setup():
        B, S, D = 1, 2048, 448
        return {
            "x": _w((lambda *s: torch.randn(*s, dtype=torch.bfloat16) * 0.05)(B, S, D)),
            "wqkv": _w((lambda *s: torch.randn(*s, dtype=torch.bfloat16) * 0.8)(D, 3 * D)),
            "wo": _w((lambda *s: torch.randn(*s, dtype=torch.bfloat16) * 0.05)(D, D)),
        }
    _A_in = _A_setup()

    def _B_setup():
        B, S, D, F = 1, 2048, 448, 1792
        return {
            "x": _w((lambda *s: torch.randn(*s, dtype=torch.bfloat16) * 0.05)(B, S, D)),
            "W_gate": _w((lambda *s: torch.randn(*s, dtype=torch.bfloat16) * 1.6)(D, F) * (2.0 / D) ** 0.5),
            "W_up": _w((lambda *s: torch.randn(*s, dtype=torch.bfloat16) * 1.6)(D, F) * (2.0 / D) ** 0.5),
            "W_down": _w((lambda *s: torch.randn(*s, dtype=torch.bfloat16) * 1.6)(F, D) * (1.0 / F) ** 0.5),
        }
    _B_in = _B_setup()

    return {
        "A_x": _A_in["x"],
        "A_wqkv": _A_in["wqkv"],
        "A_wo": _A_in["wo"],
        "B_x": _B_in["x"],
        "B_W_gate": _B_in["W_gate"],
        "B_W_up": _B_in["W_up"],
        "B_W_down": _B_in["W_down"],
        "gate_w": _w((lambda *s: torch.randn(*s, dtype=torch.bfloat16) * 0.05)(448) * 16.0),
    }

def reference(A_x, A_wqkv, A_wo, B_x, B_W_gate, B_W_up, B_W_down, gate_w):
    def _A_ref(x, wqkv, wo):
        B, S, D = x.shape
        H = 16; Dh = D // H
        qkv = (lambda x, *d: x.permute(*d))((x @ wqkv).reshape(B, S, 3, H, Dh), 2, 0, 3, 1, 4)
        q, k, v = qkv[0], qkv[1], qkv[2]
        phi = lambda t: torch.where(t > 0, t + 1, torch.exp(t)) + 1e-6
        pq, pk = phi(q), phi(k)
        kv = torch.einsum("bhsd,bhse->bhde", pk, v)
        z = torch.einsum("bhsd->bhd", pk)
        num = torch.einsum("bhqd,bhde->bhqe", pq, kv)
        den = torch.einsum("bhqd,bhd->bhq", pq, z)[..., None] + 1e-6
        o = num / den
        return (lambda x, *d: x.permute(*d))(o, 0, 2, 1, 3).reshape(B, S, D) @ wo

    def _B_ref(x, W_gate, W_up, W_down):
        gate = torch.einsum("bsd,df->bsf", x, W_gate)
        up = torch.einsum("bsd,df->bsf", x, W_up)
        gate = gate * (lambda x, dt: x.to(dt))(gate > 0, gate.dtype)
        h = gate * up
        return torch.einsum("bsf,fd->bsd", h, W_down)

    x = A_x
    g = _sigmoid((x * gate_w).sum(-1, keepdims=True))
    a = _A_ref(x, A_wqkv, A_wo)
    b = _B_ref(x, B_W_gate, B_W_up, B_W_down)
    return g * a + (1 - g) * b
```

```cpp
#include <cuda_runtime.h>
#include <cuda_bf16.h>
#include <cuda.h>
#include <stdint.h>

namespace {

constexpr int S_ = 2048, D_ = 448, F_ = 1792;
constexpr int XS_OFF = 0;
constexpr int RING_OFF = 7 * 16384;
constexpr int SCR_OFF = RING_OFF + 81920;
constexpr int BAR_OFF = RING_OFF + 7 * 16384;
constexpr int G_OFF = BAR_OFF + 384;
constexpr int SMEM_USED = G_OFF + 1024;
constexpr int SMEM_BYTES = SMEM_USED + 1024;
constexpr int NCTA = 128;
constexpr int KP = 5;
constexpr int HK = 3;
constexpr int N5 = 11;

constexpr int F_P2 = 14, F_P3 = 28, F_KVB = F_P3 + KP, F_G2 = 36, NF = 54, NBAR = 16, NX = 4, F_SCRFREE = F_P2 + N5;
__host__ __device__ constexpr int fill_of(int phase, int st) { return phase == 0 ? st : phase == 1 ? F_P2 + st : F_P3 + st + (st >= KP); }
__host__ __device__ constexpr int ld_a(int p) { return F_G2 + 5 * (p >> 1) + (p & 1) * 3; }
__host__ __device__ constexpr int ld_c(int p) { return F_G2 + 5 * (p >> 1) + 1; }
__host__ __device__ constexpr int ld_b(int p) { return F_G2 + 5 * (p >> 1) + 2 + (p & 1) * 2; }
struct Sched { int off[NF], len[NF], dep[NF][2], epar[NF]; bool rel[NF], ok; };
constexpr Sched make_sched() {
  Sched s{};
  for (int f = 0; f < NF; f++) {
    s.len[f] = 16384;
    const int u = f - F_P2, l = f - F_G2;
    if (f < F_P2) s.off[f] = RING_OFF + (f % 7) * 16384;
    else if (l >= 7 && l < 11) s.off[f] = XS_OFF + (l - 7) * 16384;
    else if (l >= 11) s.off[f] = s.off[F_G2 + (l == 11 ? 0 : l == 12 ? 2 : l == 13 ? 3 : l == 14 ? 1 : l == 15 ? 4 : l == 16 ? 5 : 7)];
    else {
      int best = -1, bt = 1000;
      for (int c = 0; c < (u < N5 ? 5 : 7); c++) {
        const int o = RING_OFF + c * 16384;
        int t = -1;
        for (int g = 0; g < f; g++) if (s.off[g] < o + 16384 && o < s.off[g] + s.len[g]) t = g;
        if (t < bt) { bt = t; best = o; }
      }
      s.off[f] = best;
    }
  }
  s.ok = true;
  for (int f = 0; f < NF; f++) {
    int n = 0;
    s.dep[f][0] = s.dep[f][1] = -1;
    for (int g = 0; g < f; g++)
      if (!s.rel[g] && s.off[g] < s.off[f] + s.len[f] && s.off[f] < s.off[g] + s.len[g]) {
        if (n == 2) s.ok = false; else s.dep[f][n++] = g;
        s.rel[g] = true;
      }
    if (f == F_G2 + 7 && !s.rel[F_G2 - 1]) s.ok = false;
  }
  for (int f = 0; f < NF; f++) {
    s.epar[f] = 0;
    for (int g = f % NBAR; g < f; g += NBAR) s.epar[f] ^= s.rel[g];
    if (f >= NBAR) {
      bool seen = false;
      for (int h = 0; h <= f; h++) for (int q = 0; q < 2; q++) if (s.dep[h][q] >= f - NBAR) seen = true;
      bool waited = !s.rel[f - NBAR];
      for (int h = 0; h <= f; h++) for (int q = 0; q < 2; q++) if (s.dep[h][q] == f - NBAR) waited = true;
      if (!seen || !waited) s.ok = false;
    }
  }
  return s;
}
constexpr Sched SCH = make_sched();
static_assert(SCH.ok && SCH.rel[12] && SCH.rel[13] && SCH.dep[F_KVB][1] < 0 && SCH.rel[SCH.dep[F_KVB][0] + 1], "fill schedule");
template <int F> struct Fill {
  [[maybe_unused]] static constexpr int off = SCH.off[F], dep0 = SCH.dep[F][0], dep1 = SCH.dep[F][1], bar = 8 * (F % NBAR), par = (F / NBAR) & 1, epar = SCH.epar[F];
  static constexpr bool rel = SCH.rel[F];
};

struct Maps {
  CUtensorMap x, qkv, g1, u1, q32, g3, u3, wd64, wd48, wo, out;
};

__device__ float4 g_kv[8][56][8];
__device__ float g_logit[S_];
__device__ unsigned g_ctr[2];

__device__ __forceinline__ uint32_t smem_u32(const void* p) { return (uint32_t)__cvta_generic_to_shared(p); }
__device__ __forceinline__ void mbar_init(uint32_t bar, uint32_t cnt) {
  asm volatile("mbarrier.init.shared::cta.b64 [%0], %1;" ::"r"(bar), "r"(cnt) : "memory");
}
__device__ __forceinline__ void mbar_expect_tx(uint32_t bar, uint32_t bytes) {
  asm volatile("mbarrier.arrive.expect_tx.shared::cta.b64 _, [%0], %1;" ::"r"(bar), "r"(bytes) : "memory");
}
__device__ __forceinline__ void mbar_arrive(uint32_t bar) {
  asm volatile("mbarrier.arrive.shared::cta.b64 _, [%0];" ::"r"(bar) : "memory");
}
__device__ __forceinline__ void mbar_arrive_cluster(uint32_t cluster_addr) {
  asm volatile("mbarrier.arrive.shared::cluster.b64 _, [%0];" ::"r"(cluster_addr) : "memory");
}
__device__ __forceinline__ void mbar_wait(uint32_t bar, uint32_t parity, uint32_t& n) {
  asm volatile(
      "{\n.reg .pred p;\n"
      "W_LOOP:\n"
      "mbarrier.try_wait.parity.shared::cta.b64 p, [%1], %2;\n"
      "@p bra W_DONE;\n"
      "add.u32 %0, %0, 1;\n"
      "setp.lt.u32 p, %0, 0x1000000;\n"
      "@p bra W_LOOP;\n"
      "trap;\n"
      "W_DONE:\n}\n" : "+r"(n) : "r"(bar), "r"(parity) : "memory");
}
template <int ID, int N> __device__ __forceinline__ void bar_sync() { asm volatile("bar.sync %0, %1;" ::"n"(ID), "n"(N) : "memory"); }
template <int ID, int N> __device__ __forceinline__ void bar_arrive() { asm volatile("bar.arrive %0, %1;" ::"n"(ID), "n"(N) : "memory"); }
__device__ __forceinline__ void fence_async_smem() { asm volatile("fence.proxy.async.shared::cta;" ::: "memory"); }
__device__ __forceinline__ void wg_fence() { asm volatile("wgmma.fence.sync.aligned;" ::: "memory"); }
__device__ __forceinline__ void wg_commit() { asm volatile("wgmma.commit_group.sync.aligned;" ::: "memory"); }
template <int N> __device__ __forceinline__ void wg_wait() { asm volatile("wgmma.wait_group.sync.aligned %0;" ::"n"(N) : "memory"); }
template <int N> __device__ __forceinline__ void reg_fence(float (&d)[N]) {
#pragma unroll
  for (int i = 0; i < N; i++) asm volatile("" : "+f"(d[i])::"memory");
}
__device__ __forceinline__ void tma2d(uint32_t dst, const CUtensorMap* m, int c0, int c1, uint32_t bar) {
  asm volatile("cp.async.bulk.tensor.2d.shared::cluster.global.mbarrier::complete_tx::bytes [%0], [%1, {%3, %4}], [%2];"
               ::"r"(dst), "l"(m), "r"(bar), "r"(c0), "r"(c1) : "memory");
}
__device__ __forceinline__ void tma2d_mc(uint32_t dst, const CUtensorMap* m, int c0, int c1, uint32_t bar) {
  asm volatile("cp.async.bulk.tensor.2d.shared::cluster.global.mbarrier::complete_tx::bytes.multicast::cluster [%0], [%1, {%3, %4}], [%2], %5;"
               ::"r"(dst), "l"(m), "r"(bar), "r"(c0), "r"(c1), "h"((uint16_t)3) : "memory");
}
__device__ __forceinline__ void tma3d_mc(uint32_t dst, const CUtensorMap* m, int c0, int c1, int c2, uint32_t bar) {
  asm volatile("cp.async.bulk.tensor.3d.shared::cluster.global.mbarrier::complete_tx::bytes.multicast::cluster [%0], [%1, {%3, %4, %5}], [%2], %6;"
               ::"r"(dst), "l"(m), "r"(bar), "r"(c0), "r"(c1), "r"(c2), "h"((uint16_t)3) : "memory");
}
__device__ __forceinline__ void tma_reduce2d(const CUtensorMap* m, int c0, int c1, uint32_t src) {
  asm volatile("cp.reduce.async.bulk.tensor.2d.global.shared::cta.add.bulk_group [%0, {%2, %3}], [%1];"
               ::"l"(m), "r"(src), "r"(c0), "r"(c1) : "memory");
}
__device__ __forceinline__ void l2_prefetch(const void* p, uint32_t bytes) {
  asm volatile("cp.async.bulk.prefetch.L2.global [%0], %1;" ::"l"(p), "r"(bytes) : "memory");
}
__device__ __forceinline__ void prefetch_map(const CUtensorMap* m) {
  asm volatile("prefetch.tensormap [%0];" ::"l"(m) : "memory");
}
__device__ __forceinline__ void stsm4(uint32_t addr, uint32_t a, uint32_t b, uint32_t c, uint32_t d) {
  asm volatile("stmatrix.sync.aligned.m8n8.x4.shared.b16 [%0], {%1,%2,%3,%4};" ::"r"(addr), "r"(a), "r"(b), "r"(c), "r"(d) : "memory");
}
__device__ __forceinline__ uint32_t pack2(float lo, float hi) {
  uint32_t r;
  asm("cvt.rn.bf16x2.f32 %0, %1, %2;" : "=r"(r) : "f"(hi), "f"(lo));
  return r;
}
__device__ __forceinline__ uint32_t pack2_relu(float lo, float hi) {
  uint32_t r;
  asm("cvt.rn.relu.bf16x2.f32 %0, %1, %2;" : "=r"(r) : "f"(hi), "f"(lo));
  return r;
}
__device__ __forceinline__ uint32_t mul2(uint32_t a, uint32_t b) {
  uint32_t r;
  asm("mul.rn.bf16x2 %0, %1, %2;" : "=r"(r) : "r"(a), "r"(b));
  return r;
}
__device__ __forceinline__ void grid_arrive(unsigned* ctr) {
  asm volatile("fence.acq_rel.gpu;" ::: "memory");
  asm volatile("red.relaxed.gpu.global.add.u32 [%0], 1;" ::"l"(ctr) : "memory");
}
__device__ __forceinline__ void grid_wait(const unsigned* ctr, unsigned target) {
  unsigned v;
  int n = 0;
  while (true) {
    asm volatile("ld.acquire.gpu.global.u32 %0, [%1];" : "=r"(v) : "l"(ctr) : "memory");
    if ((int)(v - target) >= 0) break;
    __nanosleep(32);
    if (++n > (1 << 22)) __trap();
  }
}
__device__ __forceinline__ float exp_fast(float t) {
  float e;
  asm("ex2.approx.ftz.f32 %0, %1;" : "=f"(e) : "f"(t * 1.4426950408889634f));
  return e;
}
__device__ __forceinline__ float phi(float t) { return (fmaxf(t, 0.f) + 1e-6f) + exp_fast(fminf(t, 0.f)); }
__device__ __forceinline__ uint32_t phi2(uint32_t v) { return pack2(phi(__uint_as_float(v << 16)), phi(__uint_as_float(v & 0xffff0000u))); }
__device__ __forceinline__ uint32_t desc_lo(uint32_t addr, uint32_t lbo) { return ((addr & 0x3FFFF) >> 4) | ((lbo >> 4) << 16); }
constexpr uint32_t HI_SW128 = (1024 >> 4) | (1u << 30), HI_SW64 = (512 >> 4) | (2u << 30);

template <int AO, uint32_t AHI, int BO, uint32_t BHI, int SD>
__device__ __forceinline__ void wgmma_ss_n248(float (&d)[124], uint32_t alo, uint32_t blo) {
  asm volatile("{\n.reg .pred p;\n.reg .b32 ta, tb;\n.reg .b64 da, db;\nsetp.ne.b32 p, %130, 0;\n"
    "add.u32 ta, %124, %126;\nadd.u32 tb, %125, %128;\nmov.b64 da, {ta, %127};\nmov.b64 db, {tb, %129};\n"
    "wgmma.mma_async.sync.aligned.m64n248k16.f32.bf16.bf16 "
    "{%0,%1,%2,%3,%4,%5,%6,%7,%8,%9,%10,%11,%12,%13,%14,%15,%16,%17,%18,%19,%20,%21,%22,%23,%24,%25,%26,%27,%28,%29,%30,%31,%32,%33,%34,%35,%36,%37,%38,%39,%40,%41,%42,%43,%44,%45,%46,%47,%48,%49,%50,%51,%52,%53,%54,%55,%56,%57,%58,%59,%60,%61,%62,%63,%64,%65,%66,%67,%68,%69,%70,%71,%72,%73,%74,%75,%76,%77,%78,%79,%80,%81,%82,%83,%84,%85,%86,%87,%88,%89,%90,%91,%92,%93,%94,%95,%96,%97,%98,%99,%100,%101,%102,%103,%104,%105,%106,%107,%108,%109,%110,%111,%112,%113,%114,%115,%116,%117,%118,%119,%120,%121,%122,%123}, "
    "da, db, p, 1, 1, 0, 1;\n}\n"
    : "+f"(d[0]), "+f"(d[1]), "+f"(d[2]), "+f"(d[3]), "+f"(d[4]), "+f"(d[5]), "+f"(d[6]), "+f"(d[7]), "+f"(d[8]), "+f"(d[9]), "+f"(d[10]), "+f"(d[11]), "+f"(d[12]), "+f"(d[13]), "+f"(d[14]), "+f"(d[15]), "+f"(d[16]), "+f"(d[17]), "+f"(d[18]), "+f"(d[19]), "+f"(d[20]), "+f"(d[21]), "+f"(d[22]), "+f"(d[23]), "+f"(d[24]), "+f"(d[25]), "+f"(d[26]), "+f"(d[27]), "+f"(d[28]), "+f"(d[29]), "+f"(d[30]), "+f"(d[31]), "+f"(d[32]), "+f"(d[33]), "+f"(d[34]), "+f"(d[35]), "+f"(d[36]), "+f"(d[37]), "+f"(d[38]), "+f"(d[39]), "+f"(d[40]), "+f"(d[41]), "+f"(d[42]), "+f"(d[43]), "+f"(d[44]), "+f"(d[45]), "+f"(d[46]), "+f"(d[47]), "+f"(d[48]), "+f"(d[49]), "+f"(d[50]), "+f"(d[51]), "+f"(d[52]), "+f"(d[53]), "+f"(d[54]), "+f"(d[55]), "+f"(d[56]), "+f"(d[57]), "+f"(d[58]), "+f"(d[59]), "+f"(d[60]), "+f"(d[61]), "+f"(d[62]), "+f"(d[63]), "+f"(d[64]), "+f"(d[65]), "+f"(d[66]), "+f"(d[67]), "+f"(d[68]), "+f"(d[69]), "+f"(d[70]), "+f"(d[71]), "+f"(d[72]), "+f"(d[73]), "+f"(d[74]), "+f"(d[75]), "+f"(d[76]), "+f"(d[77]), "+f"(d[78]), "+f"(d[79]), "+f"(d[80]), "+f"(d[81]), "+f"(d[82]), "+f"(d[83]), "+f"(d[84]), "+f"(d[85]), "+f"(d[86]), "+f"(d[87]), "+f"(d[88]), "+f"(d[89]), "+f"(d[90]), "+f"(d[91]), "+f"(d[92]), "+f"(d[93]), "+f"(d[94]), "+f"(d[95]), "+f"(d[96]), "+f"(d[97]), "+f"(d[98]), "+f"(d[99]), "+f"(d[100]), "+f"(d[101]), "+f"(d[102]), "+f"(d[103]), "+f"(d[104]), "+f"(d[105]), "+f"(d[106]), "+f"(d[107]), "+f"(d[108]), "+f"(d[109]), "+f"(d[110]), "+f"(d[111]), "+f"(d[112]), "+f"(d[113]), "+f"(d[114]), "+f"(d[115]), "+f"(d[116]), "+f"(d[117]), "+f"(d[118]), "+f"(d[119]), "+f"(d[120]), "+f"(d[121]), "+f"(d[122]), "+f"(d[123])
    : "r"(alo), "r"(blo), "n"(AO), "n"(AHI), "n"(BO), "n"(BHI), "n"(SD));
}
template <int AO, uint32_t AHI, int BO, uint32_t BHI, int SD>
__device__ __forceinline__ void wgmma_ss_n128(float (&d)[64], uint32_t alo, uint32_t blo) {
  asm volatile("{\n.reg .pred p;\n.reg .b32 ta, tb;\n.reg .b64 da, db;\nsetp.ne.b32 p, %70, 0;\n"
    "add.u32 ta, %64, %66;\nadd.u32 tb, %65, %68;\nmov.b64 da, {ta, %67};\nmov.b64 db, {tb, %69};\n"
    "wgmma.mma_async.sync.aligned.m64n128k16.f32.bf16.bf16 "
    "{%0,%1,%2,%3,%4,%5,%6,%7,%8,%9,%10,%11,%12,%13,%14,%15,%16,%17,%18,%19,%20,%21,%22,%23,%24,%25,%26,%27,%28,%29,%30,%31,%32,%33,%34,%35,%36,%37,%38,%39,%40,%41,%42,%43,%44,%45,%46,%47,%48,%49,%50,%51,%52,%53,%54,%55,%56,%57,%58,%59,%60,%61,%62,%63}, "
    "da, db, p, 1, 1, 0, 1;\n}\n"
    : "+f"(d[0]), "+f"(d[1]), "+f"(d[2]), "+f"(d[3]), "+f"(d[4]), "+f"(d[5]), "+f"(d[6]), "+f"(d[7]), "+f"(d[8]), "+f"(d[9]), "+f"(d[10]), "+f"(d[11]), "+f"(d[12]), "+f"(d[13]), "+f"(d[14]), "+f"(d[15]), "+f"(d[16]), "+f"(d[17]), "+f"(d[18]), "+f"(d[19]), "+f"(d[20]), "+f"(d[21]), "+f"(d[22]), "+f"(d[23]), "+f"(d[24]), "+f"(d[25]), "+f"(d[26]), "+f"(d[27]), "+f"(d[28]), "+f"(d[29]), "+f"(d[30]), "+f"(d[31]), "+f"(d[32]), "+f"(d[33]), "+f"(d[34]), "+f"(d[35]), "+f"(d[36]), "+f"(d[37]), "+f"(d[38]), "+f"(d[39]), "+f"(d[40]), "+f"(d[41]), "+f"(d[42]), "+f"(d[43]), "+f"(d[44]), "+f"(d[45]), "+f"(d[46]), "+f"(d[47]), "+f"(d[48]), "+f"(d[49]), "+f"(d[50]), "+f"(d[51]), "+f"(d[52]), "+f"(d[53]), "+f"(d[54]), "+f"(d[55]), "+f"(d[56]), "+f"(d[57]), "+f"(d[58]), "+f"(d[59]), "+f"(d[60]), "+f"(d[61]), "+f"(d[62]), "+f"(d[63])
    : "r"(alo), "r"(blo), "n"(AO), "n"(AHI), "n"(BO), "n"(BHI), "n"(SD));
}
template <int AO, uint32_t AHI, int BO, uint32_t BHI, int SD>
__device__ __forceinline__ void wgmma_ss_n256(float (&d)[128], uint32_t alo, uint32_t blo) {
  asm volatile("{\n.reg .pred p;\n.reg .b32 ta, tb;\n.reg .b64 da, db;\nsetp.ne.b32 p, %134, 0;\n"
    "add.u32 ta, %128, %130;\nadd.u32 tb, %129, %132;\nmov.b64 da, {ta, %131};\nmov.b64 db, {tb, %133};\n"
    "wgmma.mma_async.sync.aligned.m64n256k16.f32.bf16.bf16 "
    "{%0,%1,%2,%3,%4,%5,%6,%7,%8,%9,%10,%11,%12,%13,%14,%15,%16,%17,%18,%19,%20,%21,%22,%23,%24,%25,%26,%27,%28,%29,%30,%31,%32,%33,%34,%35,%36,%37,%38,%39,%40,%41,%42,%43,%44,%45,%46,%47,%48,%49,%50,%51,%52,%53,%54,%55,%56,%57,%58,%59,%60,%61,%62,%63,%64,%65,%66,%67,%68,%69,%70,%71,%72,%73,%74,%75,%76,%77,%78,%79,%80,%81,%82,%83,%84,%85,%86,%87,%88,%89,%90,%91,%92,%93,%94,%95,%96,%97,%98,%99,%100,%101,%102,%103,%104,%105,%106,%107,%108,%109,%110,%111,%112,%113,%114,%115,%116,%117,%118,%119,%120,%121,%122,%123,%124,%125,%126,%127}, "
    "da, db, p, 1, 1, 0, 1;\n}\n"
    : "+f"(d[0]), "+f"(d[1]), "+f"(d[2]), "+f"(d[3]), "+f"(d[4]), "+f"(d[5]), "+f"(d[6]), "+f"(d[7]), "+f"(d[8]), "+f"(d[9]), "+f"(d[10]), "+f"(d[11]), "+f"(d[12]), "+f"(d[13]), "+f"(d[14]), "+f"(d[15]), "+f"(d[16]), "+f"(d[17]), "+f"(d[18]), "+f"(d[19]), "+f"(d[20]), "+f"(d[21]), "+f"(d[22]), "+f"(d[23]), "+f"(d[24]), "+f"(d[25]), "+f"(d[26]), "+f"(d[27]), "+f"(d[28]), "+f"(d[29]), "+f"(d[30]), "+f"(d[31]), "+f"(d[32]), "+f"(d[33]), "+f"(d[34]), "+f"(d[35]), "+f"(d[36]), "+f"(d[37]), "+f"(d[38]), "+f"(d[39]), "+f"(d[40]), "+f"(d[41]), "+f"(d[42]), "+f"(d[43]), "+f"(d[44]), "+f"(d[45]), "+f"(d[46]), "+f"(d[47]), "+f"(d[48]), "+f"(d[49]), "+f"(d[50]), "+f"(d[51]), "+f"(d[52]), "+f"(d[53]), "+f"(d[54]), "+f"(d[55]), "+f"(d[56]), "+f"(d[57]), "+f"(d[58]), "+f"(d[59]), "+f"(d[60]), "+f"(d[61]), "+f"(d[62]), "+f"(d[63]), "+f"(d[64]), "+f"(d[65]), "+f"(d[66]), "+f"(d[67]), "+f"(d[68]), "+f"(d[69]), "+f"(d[70]), "+f"(d[71]), "+f"(d[72]), "+f"(d[73]), "+f"(d[74]), "+f"(d[75]), "+f"(d[76]), "+f"(d[77]), "+f"(d[78]), "+f"(d[79]), "+f"(d[80]), "+f"(d[81]), "+f"(d[82]), "+f"(d[83]), "+f"(d[84]), "+f"(d[85]), "+f"(d[86]), "+f"(d[87]), "+f"(d[88]), "+f"(d[89]), "+f"(d[90]), "+f"(d[91]), "+f"(d[92]), "+f"(d[93]), "+f"(d[94]), "+f"(d[95]), "+f"(d[96]), "+f"(d[97]), "+f"(d[98]), "+f"(d[99]), "+f"(d[100]), "+f"(d[101]), "+f"(d[102]), "+f"(d[103]), "+f"(d[104]), "+f"(d[105]), "+f"(d[106]), "+f"(d[107]), "+f"(d[108]), "+f"(d[109]), "+f"(d[110]), "+f"(d[111]), "+f"(d[112]), "+f"(d[113]), "+f"(d[114]), "+f"(d[115]), "+f"(d[116]), "+f"(d[117]), "+f"(d[118]), "+f"(d[119]), "+f"(d[120]), "+f"(d[121]), "+f"(d[122]), "+f"(d[123]), "+f"(d[124]), "+f"(d[125]), "+f"(d[126]), "+f"(d[127])
    : "r"(alo), "r"(blo), "n"(AO), "n"(AHI), "n"(BO), "n"(BHI), "n"(SD));
}
template <int AO, uint32_t AHI, int BO, uint32_t BHI, int SD>
__device__ __forceinline__ void wgmma_ss_n64_tt(float (&d)[32], uint32_t alo, uint32_t blo) {
  asm volatile("{\n.reg .pred p;\n.reg .b32 ta, tb;\n.reg .b64 da, db;\nsetp.ne.b32 p, %38, 0;\n"
    "add.u32 ta, %32, %34;\nadd.u32 tb, %33, %36;\nmov.b64 da, {ta, %35};\nmov.b64 db, {tb, %37};\n"
    "wgmma.mma_async.sync.aligned.m64n64k16.f32.bf16.bf16 "
    "{%0,%1,%2,%3,%4,%5,%6,%7,%8,%9,%10,%11,%12,%13,%14,%15,%16,%17,%18,%19,%20,%21,%22,%23,%24,%25,%26,%27,%28,%29,%30,%31}, "
    "da, db, p, 1, 1, 1, 1;\n}\n"
    : "+f"(d[0]), "+f"(d[1]), "+f"(d[2]), "+f"(d[3]), "+f"(d[4]), "+f"(d[5]), "+f"(d[6]), "+f"(d[7]), "+f"(d[8]), "+f"(d[9]), "+f"(d[10]), "+f"(d[11]), "+f"(d[12]), "+f"(d[13]), "+f"(d[14]), "+f"(d[15]), "+f"(d[16]), "+f"(d[17]), "+f"(d[18]), "+f"(d[19]), "+f"(d[20]), "+f"(d[21]), "+f"(d[22]), "+f"(d[23]), "+f"(d[24]), "+f"(d[25]), "+f"(d[26]), "+f"(d[27]), "+f"(d[28]), "+f"(d[29]), "+f"(d[30]), "+f"(d[31])
    : "r"(alo), "r"(blo), "n"(AO), "n"(AHI), "n"(BO), "n"(BHI), "n"(SD));
}
template <int BO, uint32_t BHI, int SD>
__device__ __forceinline__ void wgmma_rs_n64(float (&d)[32], uint32_t a0, uint32_t a1, uint32_t a2, uint32_t a3, uint32_t blo) {
  asm volatile("{\n.reg .pred p;\n.reg .b32 tb;\n.reg .b64 db;\nsetp.ne.b32 p, %39, 0;\n"
    "add.u32 tb, %36, %37;\nmov.b64 db, {tb, %38};\n"
    "wgmma.mma_async.sync.aligned.m64n64k16.f32.bf16.bf16 "
    "{%0,%1,%2,%3,%4,%5,%6,%7,%8,%9,%10,%11,%12,%13,%14,%15,%16,%17,%18,%19,%20,%21,%22,%23,%24,%25,%26,%27,%28,%29,%30,%31}, "
    "{%32,%33,%34,%35}, db, p, 1, 1, 1;\n}\n"
    : "+f"(d[0]), "+f"(d[1]), "+f"(d[2]), "+f"(d[3]), "+f"(d[4]), "+f"(d[5]), "+f"(d[6]), "+f"(d[7]), "+f"(d[8]), "+f"(d[9]), "+f"(d[10]), "+f"(d[11]), "+f"(d[12]), "+f"(d[13]), "+f"(d[14]), "+f"(d[15]), "+f"(d[16]), "+f"(d[17]), "+f"(d[18]), "+f"(d[19]), "+f"(d[20]), "+f"(d[21]), "+f"(d[22]), "+f"(d[23]), "+f"(d[24]), "+f"(d[25]), "+f"(d[26]), "+f"(d[27]), "+f"(d[28]), "+f"(d[29]), "+f"(d[30]), "+f"(d[31])
    : "r"(a0), "r"(a1), "r"(a2), "r"(a3), "r"(blo), "n"(BO), "n"(BHI), "n"(SD));
}


template <int I> struct IC { static constexpr int v = I; };
template <int N, int I = 0, class F> __device__ __forceinline__ void sfor(F&& f) {
  if constexpr (I < N) { f(IC<I>{}); sfor<N, I + 1>(f); }
}

struct Ring {
  uint32_t full, empty, empty_rel;
  uint32_t spins;
  bool sig;
  template <int F> __device__ __forceinline__ void wait() { mbar_wait(full + Fill<F>::bar, Fill<F>::par, spins); }
  template <int F> __device__ __forceinline__ void wait_free() { mbar_wait(empty + Fill<F>::bar, Fill<F>::epar, spins); }
  template <int F> __device__ __forceinline__ void release() const {
    if (Fill<F>::rel && sig) mbar_arrive_cluster(empty_rel + Fill<F>::bar);
  }
  template <int F> __device__ __forceinline__ void acquire() {
    if constexpr (Fill<F>::dep0 >= 0) wait_free<Fill<F>::dep0>();
    if constexpr (Fill<F>::dep1 >= 0) wait_free<Fill<F>::dep1>();
  }
};

template <int N, int PH, class Pre, class Post>
__device__ __forceinline__ void gemm1(float (&acc)[N / 2], Ring& r, uint32_t alo, uint32_t blo, uint32_t xfull, int wgi, Pre&& pre, Post&& post) {
  sfor<PH == 2 ? 7 : 14>([&](auto ic) {
    constexpr int st = decltype(ic)::v, f = fill_of(PH, st);
    if (f == 9 && wgi) bar_sync<5, 256>();
    if (f == 31 && wgi) bar_sync<12, 256>();
    if (PH == 0 && (st & 1) == 0) mbar_wait(xfull + 4 * st, 0, r.spins);
    r.template wait<f>();
    [[maybe_unused]] constexpr int a = (st >> 1) * 1024 + (st & 1) * 4, b = Fill<f>::off >> 4;
    wg_fence();
    if constexpr (N == 256) { wgmma_ss_n256<a, HI_SW128, b, HI_SW128, st>(acc, alo, blo); wgmma_ss_n256<a + 2, HI_SW128, b + 128, HI_SW128, 1>(acc, alo, blo); }
    if constexpr (N == 248) { wgmma_ss_n248<a, HI_SW128, b, HI_SW64, st>(acc, alo, blo); wgmma_ss_n248<a + 2, HI_SW128, b + 64, HI_SW64, 1>(acc, alo, blo); }
    if constexpr (N == 128)
      sfor<4>([&](auto kc) { constexpr int k = decltype(kc)::v; wgmma_ss_n128<st * 1024 + 2 * k, HI_SW128, b + k * 128, HI_SW128, st + k>(acc, alo, blo); });
    wg_commit();
    if (f == 11 && !wgi) bar_arrive<5, 256>();
    if (f == 32 && !wgi) bar_arrive<12, 256>();
    pre(ic);
    if constexpr (st > 0) { wg_wait<1>(); r.template release<fill_of(PH, st > 0 ? st - 1 : 0)>(); }
    post(ic);
  });
}

__global__ void __cluster_dims__(2, 1, 1) __launch_bounds__(384, 1)
fused_kernel(const __grid_constant__ Maps maps, const __nv_bfloat16* __restrict__ wqkv, const __nv_bfloat16* __restrict__ wo,
             const __nv_bfloat16* __restrict__ wg, const __nv_bfloat16* __restrict__ wu, const __nv_bfloat16* __restrict__ wd,
             const __nv_bfloat16* __restrict__ gate_w, const __nv_bfloat16* __restrict__ x, __nv_bfloat16* __restrict__ out) {
  extern __shared__ uint8_t smem_raw[];
  const uint32_t sb = (smem_u32(smem_raw) + 1023) & ~1023u;
  const uint32_t xs = sb + XS_OFF;
  const uint32_t full = sb + BAR_OFF, empty = full + 8 * NBAR, xfull = empty + 8 * NBAR, sfree = xfull + 8 * 7, scrfree = sfree + 16;
  const int tid = threadIdx.x, lane = tid & 31;
  const int rank = blockIdx.x & 1, j = blockIdx.x >> 4, m = blockIdx.x & 15;
  const int odd = j & 1;
  const int f1 = 224 * j + odd * 160, f2 = 224 * j + 64 + odd * 32, f3 = 224 * j + 128 - odd * 128;
  const int a0 = j == 7 ? 0 : j;

  const int warp = __shfl_sync(0xffffffffu, tid >> 5, 0);
  const CUtensorMap* m1 = rank ? &maps.u1 : &maps.g1;
  if (lane == 0) {
    if (warp == 8) {
      mbar_init(xfull, 1);
      mbar_expect_tx(xfull, 16384);
      tma2d(xs, &maps.x, 0, m * 128, xfull);
    } else if (warp == 9) {
      prefetch_map(m1);
      prefetch_map(&maps.qkv);
    } else if (warp < 8) {
      mbar_init(full + 8 * warp, 1);
      mbar_init(full + 8 * warp + 64, 1);
      mbar_init(empty + 8 * warp, 4);
      mbar_init(empty + 8 * warp + 64, 4);
    } else {
      const uint32_t b = xfull + 8 + (warp - 10) * 32;
      for (int i = 0; i < 4; i++) mbar_init(b + 8 * i, 1);
      if (warp == 11) mbar_init(scrfree, 2);
    }
    asm volatile("fence.mbarrier_init.release.cluster;" ::: "memory");
  }
  __syncwarp();
  asm volatile("barrier.cluster.arrive.relaxed.aligned;\nbarrier.cluster.wait.aligned;" ::: "memory");
  auto issue = [&](auto fc) {
    constexpr int f = decltype(fc)::v;
    const uint32_t dst = sb + Fill<f>::off, bar = full + Fill<f>::bar;
    if constexpr (f < F_P2) {
      mbar_expect_tx(bar, 16384);
      tma2d_mc(dst + rank * 4096, m1, f1, f * 32, bar);
      tma2d_mc(dst + 8192 + rank * 4096, &maps.qkv, (1 + rank) * D_ + 56 * j - 8 * (j & 1), f * 32, bar);
      if constexpr ((f & 1) && f < 13) {
        mbar_expect_tx(xfull + 4 * (f + 1), 16384);
        tma2d(xs + (f + 1) * 8192, &maps.x, 32 * (f + 1), m * 128, xfull + 4 * (f + 1));
      }
    } else if constexpr (f < F_P3) {
      mbar_expect_tx(bar, 16384);
      tma3d_mc(dst + rank * 6144, rank ? &maps.u3 : &maps.g3, 0, (f - F_P2) * 32, f3 >> 5, bar);
      tma2d_mc(dst + 12288 + rank * 2048, &maps.q32, 56 * j + 32 * rank, (f - F_P2) * 32, bar);
    } else if constexpr (f < F_G2) {
      mbar_expect_tx(bar, 16384);
      tma2d_mc(dst + rank * 8192, m1, f2, (f - F_P3 - (f > F_KVB)) * 64, bar);
      tma2d_mc(dst + rank * 8192 + 4096, m1, f2, (f - F_P3 - (f > F_KVB)) * 64 + 32, bar);
    } else {
      constexpr int q = (f - F_G2) % 5, p = 2 * ((f - F_G2) / 5) + (q >= 3);
      const int a = a0 + p >= 7 ? a0 + p - 7 : a0 + p;
      if constexpr (q == 1) {
        mbar_expect_tx(bar, p < 6 ? 16384 : 8192);
        tma2d_mc(dst + rank * 4096, &maps.wo, 64 * a, 56 * j + rank * 32, bar);
        if (p < 6) tma2d_mc(dst + 8192 + rank * 4096, &maps.wo, a == 6 ? 0 : 64 * a + 64, 56 * j + rank * 32, bar);
      } else {
        mbar_expect_tx(bar, 14336);
        if constexpr (q == 0 || q == 3) {
          if (rank) tma2d_mc(dst + 8192, &maps.wd48, 64 * a, f3, bar); else tma2d_mc(dst, &maps.wd64, 64 * a, f1, bar);
        } else {
          if (rank) tma2d_mc(dst, &maps.wd48, 64 * a, f3 + 48, bar); else tma2d_mc(dst + 6144, &maps.wd64, 64 * a, f2, bar);
        }
      }
    }
  };
  if (warp == 8 && lane == 0) { issue(IC<0>{}); issue(IC<1>{}); }
  __syncwarp();

  if (warp >= 8) {
    asm volatile("setmaxnreg.dec.sync.aligned.u32 40;");
    Ring r;
    r.full = full; r.empty = empty; r.spins = 0;
    uint32_t& spins = r.spins;
    if (warp == 8) {
      if (lane == 0) {
        sfor<NF, 2>([&](auto fc) {
          constexpr int f = decltype(fc)::v;
          r.template acquire<f>();
          if constexpr (f == F_SCRFREE) mbar_wait(scrfree, 0, spins);
          if constexpr (f != F_KVB) issue(fc);
          if constexpr (f == 6) {
            prefetch_map(rank ? &maps.u3 : &maps.g3);
            prefetch_map(&maps.q32);
            prefetch_map(rank ? &maps.wd48 : &maps.wd64);
            prefetch_map(&maps.wo);
            prefetch_map(&maps.out);
          }
        });
      }
    } else {
      const int ht = tid - 288, hw = warp - 9;
      unsigned target = 0;
      if (hw == 0) {
        unsigned c0;
        asm volatile("ld.relaxed.gpu.global.u32 %0, [%1];" : "=r"(c0) : "l"(&g_ctr[0]) : "memory");
        if (lane < 28) (&g_kv[0][0][0])[blockIdx.x * 28 + lane] = make_float4(0, 0, 0, 0);
        __syncwarp();
        target = (c0 / NCTA + 1) * NCTA;
        if (lane == 0) { grid_arrive(&g_ctr[0]); grid_wait(&g_ctr[0], target); }
        __syncwarp();
      } else {
        const int l = lane < 28 ? lane : 0;
        const uint4 w0 = __ldg(reinterpret_cast<const uint4*>(gate_w) + 2 * l), w1 = __ldg(reinterpret_cast<const uint4*>(gate_w) + 2 * l + 1);
        const uint32_t w[8] = {w0.x, w0.y, w0.z, w0.w, w1.x, w1.y, w1.z, w1.w};
        const int row0 = m * 128 + j * 16 + (hw - 1) * 8;
#pragma unroll 1
        for (int rb = 0; rb < 8; rb += 2) {
          uint4 v0[2], v1[2];
#pragma unroll
          for (int q = 0; q < 2; q++) {
            const uint4* xr = reinterpret_cast<const uint4*>(x + (size_t)(row0 + rb + q) * D_) + 2 * l;
            v0[q] = __ldg(xr); v1[q] = __ldg(xr + 1);
          }
#pragma unroll
          for (int q = 0; q < 2; q++) {
            const uint32_t v[8] = {v0[q].x, v0[q].y, v0[q].z, v0[q].w, v1[q].x, v1[q].y, v1[q].z, v1[q].w};
            float s0 = 0.f, s1 = 0.f;
#pragma unroll
            for (int e = 0; e < 8; e++) {
              s0 = fmaf(__uint_as_float(v[e] << 16), __uint_as_float(w[e] << 16), s0);
              s1 = fmaf(__uint_as_float(v[e] & 0xffff0000u), __uint_as_float(w[e] & 0xffff0000u), s1);
            }
            float sum = lane < 28 ? s0 + s1 : 0.f;
#pragma unroll
            for (int o = 16; o > 0; o >>= 1) sum += __shfl_xor_sync(0xffffffffu, sum, o);
            if (lane == 0) g_logit[row0 + rb + q] = sum;
          }
        }
        mbar_wait(xfull + 8 * 3, 0, spins);
        if (ht == 32) {
          l2_prefetch(wg + (size_t)blockIdx.x * (D_ * F_ / NCTA), D_ * F_ * 2 / NCTA);
          l2_prefetch(wu + (size_t)blockIdx.x * (D_ * F_ / NCTA), D_ * F_ * 2 / NCTA);
          l2_prefetch(wqkv + (size_t)blockIdx.x * (D_ * 3 * D_ / NCTA), D_ * 3 * D_ * 2 / NCTA);
        }
        mbar_wait(xfull + 8 * 6, 0, spins);
        if (ht == 32) {
          l2_prefetch(wd + (size_t)blockIdx.x * (D_ * F_ / NCTA), D_ * F_ * 2 / NCTA);
          l2_prefetch(wo + (size_t)blockIdx.x * (D_ * D_ / NCTA), D_ * D_ * 2 / NCTA);
        }
        uint4* o4 = reinterpret_cast<uint4*>(out + (size_t)(m * 128 + j * 16) * D_) + (ht - 32);
#pragma unroll
        for (int i = 0; i < 14; i++) o4[i * 64] = make_uint4(0, 0, 0, 0);
      }
      const uint32_t kvb = sb + Fill<F_KVB>::off;
      uint32_t dsta[5];
#pragma unroll
      for (int i = 0; i < 5; i++) {
        const int d = (ht >> 3) + 12 * i, q = (ht ^ d) & 7;
        dsta[i] = kvb + d * 128 + (((q == 7 ? 14 : d >= 28 ? 7 + q : q) * 8) ^ ((d & 7) << 4)) + (q == 7) + 2 * (d >= 28);
        asm volatile("" : "+r"(dsta[i]));
      }
      bar_sync<3, 352>();
      {
        float4 v[5];
#pragma unroll
        for (int i = 0; i < 5; i++) {
          const uint32_t a = sb + SCR_OFF + (i < 4 || ht < 64 ? ht + 96 * i : 0) * 16;
          float4 u;
          asm volatile("ld.shared.v4.f32 {%0,%1,%2,%3}, [%4];" : "=f"(v[i].x), "=f"(v[i].y), "=f"(v[i].z), "=f"(v[i].w) : "r"(a) : "memory");
          asm volatile("ld.shared.v4.f32 {%0,%1,%2,%3}, [%4];" : "=f"(u.x), "=f"(u.y), "=f"(u.z), "=f"(u.w) : "r"(a + 16384) : "memory");
          v[i].x += u.x; v[i].y += u.y; v[i].z += u.z; v[i].w += u.w;
        }
        fence_async_smem();
        bar_sync<4, 96>();
        if (ht < 2) {
          uint32_t ra;
          asm volatile("mapa.shared::cluster.u32 %0, %1, %2;" : "=r"(ra) : "r"(scrfree), "r"(ht));
          mbar_arrive_cluster(ra);
        }
#pragma unroll
        for (int i = 0; i < 5; i++)
          if (i < 4 || ht < 64) {
            asm volatile("red.relaxed.gpu.global.add.v4.f32 [%0], {%1,%2,%3,%4};" ::"l"(&g_kv[j][0][0] + ht + 96 * i),
                         "f"(v[i].x), "f"(v[i].y), "f"(v[i].z), "f"(v[i].w) : "memory");
          }
      }
      bar_sync<4, 96>();
      if (ht == 0) {
        grid_arrive(&g_ctr[1]);
        grid_wait(&g_ctr[1], target);
      }
      if (hw) {
        r.template acquire<F_KVB>();
        r.template wait_free<Fill<F_KVB>::dep0 + 1>();
#pragma unroll
        for (int i = 0; i < 8; i++) asm volatile("st.shared.v4.b32 [%0], {%1,%1,%1,%1};" ::"r"(kvb + (ht - 32) * 16 + i * 1024), "r"(0) : "memory");
      }
      __syncwarp();
      bar_sync<4, 96>();
      {
        const float lg0 = __ldcg(&g_logit[m * 128 + ht]), lg1 = __ldcg(&g_logit[m * 128 + 96 + (ht & 31)]);
        float4 v[5];
#pragma unroll
        for (int i = 0; i < 5; i++) v[i] = __ldcg(&g_kv[j][0][0] + (i < 4 || ht < 64 ? ht + 96 * i : 0));
        const float r0 = exp_fast(fminf(lg0, 40.f)), r1 = exp_fast(fminf(lg1, 40.f));
        asm volatile("st.shared.v2.f32 [%0], {%1,%2};" ::"r"(sb + G_OFF + ht * 8), "f"(r0), "f"(__fdividef(1.f, 1.f + r0)) : "memory");
        asm volatile("st.shared.v2.f32 [%0], {%1,%2};" ::"r"(sb + G_OFF + (96 + (ht & 31)) * 8), "f"(r1), "f"(__fdividef(1.f, 1.f + r1)) : "memory");
#pragma unroll
        for (int i = 0; i < 5; i++) {
          const uint32_t lo = pack2(v[i].x, v[i].y), hi = pack2(v[i].z, v[i].w), z = (dsta[i] & 2) ? lo << 16 : lo & 0xffffu;
          const int live = i < 4 || ht < 64, isz = dsta[i] & 1;
          asm volatile("{\n.reg .pred p, q;\nsetp.ne.b32 p, %4, 0;\nsetp.ne.b32 q, %5, 0;\n"
                       "@p st.shared.v2.b32 [%0], {%1,%2};\n@q st.shared.v4.b32 [%0], {%3,%3,%3,%3};\n}"
                       ::"r"(dsta[i] & ~3u), "r"(lo), "r"(hi), "r"(z), "r"(live & ~isz), "r"(live & isz) : "memory");
        }
      }
      fence_async_smem();
      bar_sync<4, 96>();
      if (ht == 0) mbar_arrive(full + Fill<F_KVB>::bar);
      if (hw < 2) {
        int a = a0, buf = 0;
        asm volatile("fence.proxy.async.global;" ::: "memory");
#pragma unroll 1
        for (int p = 0; p < 7; p++) {
          if (hw) { if (p & 1) bar_sync<11, 160>(); else bar_sync<10, 160>(); }
          else { if (p & 1) bar_sync<9, 160>(); else bar_sync<8, 160>(); }
          if (lane == 0) {
            tma_reduce2d(&maps.out, 64 * a, m * 128 + hw * 64, xs + (NX + buf) * 16384 + hw * 8192);
            asm volatile("cp.async.bulk.commit_group;" ::: "memory");
            if (p >= 6 - NX && p < 6) {
              asm volatile("cp.async.bulk.wait_group.read %0;" ::"n"(6 - NX) : "memory");
              mbar_arrive(sfree + 8 * hw);
            }
          }
          __syncwarp();
          if (++a == 7) a = 0;
          if (++buf == 7 - NX) buf = 0;
        }
        if (lane == 0) asm volatile("cp.async.bulk.wait_group 0;" ::: "memory");
      }
    }
  } else {
    asm volatile("setmaxnreg.inc.sync.aligned.u32 232;");
    const int wgi = warp >> 2, wq = warp & 3;
    Ring r;
    r.full = full; r.empty = empty; r.spins = 0; r.sig = (lane == 0 && wq < 2);
    asm volatile("mapa.shared::cluster.u32 %0, %1, %2;" : "=r"(r.empty_rel) : "r"(empty), "r"(wq & 1));
    const uint32_t xlo = desc_lo(xs + wgi * 8192, 16), blo = desc_lo(sb, 2048), blo4 = desc_lo(sb, 4096), blo8 = desc_lo(sb, 8192), slo = desc_lo(sb, 16);
    const int t4 = lane & 3, g8 = lane >> 2;
    const int srow = wq * 16 + (lane & 7) + ((lane >> 3) & 1) * 8;
    const uint32_t sts_row = srow * 128, sts_x = (lane >> 4) ^ (lane & 7);

    uint32_t hf[56], pk[16], pv[16], pq[16], of[16];
    float w0, w1;
    auto nop = [](auto) {};
    {
      float acc[128];
      gemm1<256, 0>(acc, r, xlo, blo4, xfull, wgi, nop, nop);
      wg_wait<0>();
      reg_fence(acc);
      if (wgi) bar_sync<2, 128>(); else bar_sync<1, 128>();
      r.release<fill_of(0, 13)>();
#pragma unroll
      for (int i = 0; i < 16; i++) hf[i] = mul2(pack2_relu(acc[2 * i], acc[2 * i + 1]), pack2(acc[32 + 2 * i], acc[33 + 2 * i]));
      if (j & 1) {
#pragma unroll
        for (int i = 0; i < 14; i++) { pk[i] = pack2(acc[68 + 2 * i], acc[69 + 2 * i]); pv[i] = pack2(acc[100 + 2 * i], acc[101 + 2 * i]); }
      } else {
#pragma unroll
        for (int i = 0; i < 14; i++) { pk[i] = pack2(acc[64 + 2 * i], acc[65 + 2 * i]); pv[i] = pack2(acc[96 + 2 * i], acc[97 + 2 * i]); }
      }
      pk[14] = pk[15] = 0;
      pv[14] = pv[15] = (t4 == 0) ? 0x3F803F80u : 0u;
    }
    float acc2[124];
    auto p2_epilogue = [&]() {
      reg_fence(acc2);
      r.release<fill_of(1, 13)>();
#pragma unroll
      for (int i = 0; i < 24; i++) hf[16 + i] = mul2(pack2_relu(acc2[2 * i], acc2[2 * i + 1]), pack2(acc2[48 + 2 * i], acc2[49 + 2 * i]));
#pragma unroll
      for (int i = 0; i < 14; i++) pq[i] = pack2(acc2[96 + 2 * i], acc2[97 + 2 * i]);
      pq[14] = pq[15] = 0;
    };
    {
      float kv[32];
      const uint32_t scr = sb + SCR_OFF + wgi * 16384;
      auto st_tile = [&](uint32_t base, int i, const uint32_t (&v)[16]) {
        stsm4(base + sts_row + (((2 * i) ^ sts_x) << 4), v[4 * i], v[4 * i + 1], v[4 * i + 2], v[4 * i + 3]);
      };
      auto pre = [&](auto ic) {
        constexpr int st = decltype(ic)::v;
        if constexpr (st == 0) {
#pragma unroll
          for (int i = 0; i < 8; i++) pk[i] = phi2(pk[i]);
        }
        if constexpr (st == 1) {
          r.template wait_free<12>(); r.template wait_free<13>();
          st_tile(scr, 0, pk); st_tile(scr, 1, pk); st_tile(scr + 8192, 0, pv); st_tile(scr + 8192, 1, pv);
#pragma unroll
          for (int i = 8; i < 14; i++) pk[i] = phi2(pk[i]);
        }
        if constexpr (st == 2) { st_tile(scr, 2, pk); st_tile(scr, 3, pk); st_tile(scr + 8192, 2, pv); st_tile(scr + 8192, 3, pv); }
        if constexpr (st == HK) {
          fence_async_smem();
          if (wgi) bar_sync<2, 128>(); else bar_sync<1, 128>();
          const uint32_t da = slo + (SCR_OFF >> 4) + wgi * 1024;
          wg_fence();
          sfor<4>([&](auto kc) { constexpr int k = decltype(kc)::v; wgmma_ss_n64_tt<k * 128, HI_SW128, 512 + k * 128, HI_SW128, k>(kv, da, da); });
          wg_commit();
        }
      };
      auto post = [&](auto ic) {
        constexpr int st = decltype(ic)::v;
        if constexpr (st == HK + 1) {
          reg_fence(kv);
          if (wgi) bar_sync<2, 128>(); else bar_sync<1, 128>();
#pragma unroll
          for (int hh = 0; hh < 2; hh++) {
            const int d = wq * 16 + g8 + hh * 8;
            const int p0 = d < 28, p1 = d >= 28 && d < 56;
            const int pm = t4 < 2 ? p0 : p1, pz = t4 == 0 && d < 56;
            const uint32_t rw = scr + d * 128, sw = g8 << 4, c0 = t4 * 8 - (p1 ? 112 : 0);
#pragma unroll
            for (int i = 0; i < 7; i++)
              asm volatile("{\n.reg .pred p;\nsetp.ne.b32 p, %3, 0;\n@p st.shared.v2.f32 [%0], {%1,%2};\n}"
                           ::"r"(rw + ((c0 + 32 * i) ^ sw)), "f"(kv[4 * i + 2 * hh]), "f"(kv[4 * i + 2 * hh + 1]), "r"(i < 3 ? p0 : i == 3 ? pm : p1) : "memory");
            asm volatile("{\n.reg .pred p;\nsetp.ne.b32 p, %2, 0;\n@p st.shared.v4.f32 [%0], {%1,%1,%1,%1};\n}"
                         ::"r"(rw + (112 ^ sw)), "f"(kv[28 + 2 * hh]), "r"(pz) : "memory");
          }
          bar_arrive<3, 352>();
        }
      };
      gemm1<248, 1>(acc2, r, xlo, blo, 0, wgi, pre, post);
    }
    {
      float acc1[64], acc[32];
      auto pre = [&](auto ic) {
        constexpr int st = decltype(ic)::v;
        if constexpr (st == 0) { wg_wait<1>(); p2_epilogue(); }
        if constexpr (st >= 1 && st < 4) {
#pragma unroll
          for (int i = (st - 1) * 14 / 3; i < st * 14 / 3; i++) pq[i] = phi2(pq[i]);
        }
        if constexpr (st == KP) {
          r.template wait<F_KVB>();
          wg_fence();
          sfor<4>([&](auto kc) {
            constexpr int k = decltype(kc)::v;
            wgmma_rs_n64<(Fill<F_KVB>::off >> 4) + k * 128, HI_SW128, k>(acc, pq[4 * k], pq[4 * k + 1], pq[4 * k + 2], pq[4 * k + 3], slo);
          });
          wg_commit();
        }
      };
      auto post = [&](auto ic) {
        constexpr int st = decltype(ic)::v;
        if constexpr (st == KP + 1) {
          reg_fence(acc);
          r.template release<F_KVB>();
          float r0, r1;
          asm volatile("ld.shared.v2.f32 {%0,%1}, [%2];" : "=f"(r0), "=f"(w0) : "r"(sb + G_OFF + (wgi * 64 + wq * 16 + g8) * 8) : "memory");
          asm volatile("ld.shared.v2.f32 {%0,%1}, [%2];" : "=f"(r1), "=f"(w1) : "r"(sb + G_OFF + (wgi * 64 + wq * 16 + g8 + 8) * 8) : "memory");
          const float a0 = __fdividef(r0, acc[28] + 1e-6f), b0 = __fdividef(r0, acc[29] + 1e-6f);
          const float a1 = __fdividef(r1, acc[30] + 1e-6f), b1 = __fdividef(r1, acc[31] + 1e-6f);
#pragma unroll
          for (int i = 0; i < 7; i++) {
            const bool h1 = i > 3 || (i == 3 && t4 >= 2);
            const float u0 = h1 ? b0 : a0, u1 = h1 ? b1 : a1;
            of[2 * i] = pack2(acc[4 * i] * u0, acc[4 * i + 1] * u0);
            of[2 * i + 1] = pack2(acc[4 * i + 2] * u1, acc[4 * i + 3] * u1);
          }
          of[14] = of[15] = 0;
        }
      };
      gemm1<128, 2>(acc1, r, xlo, blo8, 0, wgi, pre, post);
      const uint32_t stg = xs + NX * 16384 + wgi * 8192;
      if (wgi) {
        wg_wait<0>();
        r.template release<fill_of(2, 6)>();
        bar_sync<6, 256>();
      }
      sfor<7>([&](auto pc) {
        constexpr int p = decltype(pc)::v, la = ld_a(p), lc = ld_c(p), lb = ld_b(p);
        if constexpr (p == 0) { r.template wait<la>(); r.template wait<lc>(); }
        if constexpr (p == 1) r.template wait<la>();
        wg_fence();
        sfor<7>([&](auto ic) {
          constexpr int k = decltype(ic)::v;
          wgmma_rs_n64<(Fill<la>::off >> 4) + k * 128, HI_SW128, k>(acc, hf[4 * k], hf[4 * k + 1], hf[4 * k + 2], hf[4 * k + 3], slo);
        });
        wg_commit();
        sfor<4>([&](auto ic) {
          constexpr int k = decltype(ic)::v;
          wgmma_rs_n64<(Fill<lc>::off >> 4) + (p & 1) * 512 + k * 128, HI_SW128, 1>(acc, of[4 * k], of[4 * k + 1], of[4 * k + 2], of[4 * k + 3], slo);
        });
        wg_commit();
        if constexpr (p == 0) {
          wg_wait<2>();
          reg_fence(acc1);
          if (!wgi) r.template release<fill_of(2, 6)>();
#pragma unroll
          for (int i = 0; i < 16; i++) hf[40 + i] = mul2(pack2_relu(acc1[2 * i], acc1[2 * i + 1]), pack2(acc1[32 + 2 * i], acc1[33 + 2 * i]));
          r.template wait<lb>();
          wg_fence();
        }
        if constexpr (p == 1) { r.template wait<lb>(); wg_fence(); }
        sfor<7>([&](auto ic) {
          constexpr int k = decltype(ic)::v;
          wgmma_rs_n64<(Fill<lb>::off >> 4) + k * 128, HI_SW128, 1>(acc, hf[28 + 4 * k], hf[29 + 4 * k], hf[30 + 4 * k], hf[31 + 4 * k], slo);
        });
        wg_commit();
        if (p == 0 && !wgi) bar_arrive<6, 256>();
        if constexpr (p > 0 && p < 6) {
          r.template wait<ld_a(p + 1)>();
          if (p & 1) r.template wait<ld_c(p + 1)>();
          r.template wait<ld_b(p + 1)>();
        }
        wg_wait<1>();
        r.template release<la>();
        if (p & 1) r.template release<lc>();
        wg_wait<0>();
        reg_fence(acc);
        r.template release<lb>();
        if constexpr (p >= 7 - NX) mbar_wait(sfree + 8 * wgi, (p - 7 + NX) & 1, r.spins);
#pragma unroll
        for (int i = 0; i < 4; i++)
          stsm4(stg + (p % (7 - NX)) * 16384 + sts_row + (((2 * i) ^ sts_x) << 4), pack2(acc[8 * i] * w0, acc[8 * i + 1] * w0),
                pack2(acc[8 * i + 2] * w1, acc[8 * i + 3] * w1), pack2(acc[8 * i + 4] * w0, acc[8 * i + 5] * w0),
                pack2(acc[8 * i + 6] * w1, acc[8 * i + 7] * w1));
        fence_async_smem();
        if (wgi) bar_arrive<10 + (p & 1), 160>(); else bar_arrive<8 + (p & 1), 160>();
      });
    }
  }
}

__device__ __nv_bfloat16 fb_qkv[S_ * 3 * D_], fb_oh[S_ * (D_ + F_)];
__device__ float fb_kv[16 * 28 * 29];
__device__ __forceinline__ float fb_dot(const __nv_bfloat16* a, const __nv_bfloat16* b, int ldb, int n) {
  float s = 0.f;
  for (int k = 0; k < n; k++) s = fmaf(__bfloat162float(a[k]), __bfloat162float(b[(size_t)k * ldb]), s);
  return s;
}
__global__ void fb_proj(const __nv_bfloat16* x, const __nv_bfloat16* wqkv, const __nv_bfloat16* wg, const __nv_bfloat16* wu) {
  const int t = blockIdx.y, c = blockIdx.x * 224 + threadIdx.x;
  const __nv_bfloat16* xr = x + (size_t)t * D_;
  if (c < 3 * D_) {
    const float v = __bfloat162float(__float2bfloat16(fb_dot(xr, wqkv + c, 3 * D_, D_)));
    fb_qkv[(size_t)t * 3 * D_ + c] = __float2bfloat16(c < 2 * D_ ? phi(v) : v);
  } else {
    const int f = c - 3 * D_;
    fb_oh[(size_t)t * (D_ + F_) + D_ + f] = __float2bfloat16(fmaxf(fb_dot(xr, wg + f, F_, D_), 0.f) * fb_dot(xr, wu + f, F_, D_));
  }
}
__global__ void fb_kvsum() {
  const int h = blockIdx.x, d = threadIdx.x / 29, e = threadIdx.x % 29;
  float s = 0.f;
  for (int t = 0; t < S_; t++) {
    const __nv_bfloat16* r = fb_qkv + (size_t)t * 3 * D_ + h * 28;
    s = fmaf(__bfloat162float(r[D_ + d]), e < 28 ? __bfloat162float(r[2 * D_ + e]) : 1.f, s);
  }
  fb_kv[(h * 28 + d) * 29 + e] = s;
}
__global__ void fb_attn() {
  const int t = blockIdx.x, c = threadIdx.x, h = c / 28;
  float num = 0.f, den = 0.f;
  for (int d = 0; d < 28; d++) {
    const float q = __bfloat162float(fb_qkv[(size_t)t * 3 * D_ + h * 28 + d]);
    num = fmaf(q, fb_kv[(h * 28 + d) * 29 + c % 28], num);
    den = fmaf(q, fb_kv[(h * 28 + d) * 29 + 28], den);
  }
  fb_oh[(size_t)t * (D_ + F_) + c] = __float2bfloat16(num / (den + 1e-6f));
}
__global__ void fb_out(const __nv_bfloat16* x, const __nv_bfloat16* gw, const __nv_bfloat16* wo, const __nv_bfloat16* wd, __nv_bfloat16* out) {
  const int t = blockIdx.x, c = threadIdx.x;
  const __nv_bfloat16* r = fb_oh + (size_t)t * (D_ + F_);
  const float g = 1.f / (1.f + __expf(-fb_dot(x + (size_t)t * D_, gw, 1, D_)));
  out[(size_t)t * D_ + c] = __float2bfloat16(g * fb_dot(r, wo + c, D_, D_) + (1.f - g) * fb_dot(r + D_, wd + c, D_, F_));
}

typedef CUresult (*EncodeFn)(CUtensorMap*, CUtensorMapDataType, cuuint32_t, void*, const cuuint64_t*, const cuuint64_t*,
                             const cuuint32_t*, const cuuint32_t*, CUtensorMapInterleave, CUtensorMapSwizzle,
                             CUtensorMapL2promotion, CUtensorMapFloatOOBfill);

void encode(EncodeFn fn, CUtensorMap* m, const void* base, int rank, const cuuint64_t* dims, const cuuint64_t* strides,
            const cuuint32_t* box, CUtensorMapSwizzle sw) {
  const cuuint32_t es[3] = {1, 1, 1};
  fn(m, CU_TENSOR_MAP_DATA_TYPE_BFLOAT16, rank, const_cast<void*>(base), dims, strides, box, es,
     CU_TENSOR_MAP_INTERLEAVE_NONE, sw, CU_TENSOR_MAP_L2_PROMOTION_L2_128B, CU_TENSOR_MAP_FLOAT_OOB_FILL_NONE);
}

}

extern "C" void kernel_launch(void* const* d_in, const int* in_sizes, int n_in, void* d_out, int out_size) {
  (void)in_sizes; (void)n_in; (void)out_size;
  const __nv_bfloat16* x = (const __nv_bfloat16*)d_in[0];
  const __nv_bfloat16* wqkv = (const __nv_bfloat16*)d_in[1];
  const __nv_bfloat16* wo = (const __nv_bfloat16*)d_in[2];
  const __nv_bfloat16* wg = (const __nv_bfloat16*)d_in[4];
  const __nv_bfloat16* wu = (const __nv_bfloat16*)d_in[5];
  const __nv_bfloat16* wd = (const __nv_bfloat16*)d_in[6];
  const __nv_bfloat16* gw = (const __nv_bfloat16*)d_in[7];

  static EncodeFn fn = nullptr;
  static int resident = 0;
  if (!fn) {
    void* p = nullptr;
    cudaDriverEntryPointQueryResult q;
    cudaGetDriverEntryPoint("cuTensorMapEncodeTiled", &p, cudaEnableDefault, &q);
    fn = (EncodeFn)p;
    cudaFuncSetAttribute(fused_kernel, cudaFuncAttributeMaxDynamicSharedMemorySize, SMEM_BYTES);
    cudaLaunchConfig_t cfg = {};
    cudaLaunchAttribute at;
    at.id = cudaLaunchAttributeClusterDimension;
    at.val.clusterDim.x = 2; at.val.clusterDim.y = 1; at.val.clusterDim.z = 1;
    cfg.gridDim = dim3(NCTA); cfg.blockDim = dim3(384); cfg.dynamicSmemBytes = SMEM_BYTES; cfg.attrs = &at; cfg.numAttrs = 1;
    if (cudaOccupancyMaxActiveClusters(&resident, fused_kernel, &cfg) != cudaSuccess) { resident = NCTA / 2; (void)cudaGetLastError(); }
  }
  if (resident < NCTA / 2) {
    fb_proj<<<dim3((3 * D_ + F_) / 224, S_), 224, 0, cudaStreamPerThread>>>(x, wqkv, wg, wu);
    fb_kvsum<<<16, 28 * 29, 0, cudaStreamPerThread>>>();
    fb_attn<<<S_, D_, 0, cudaStreamPerThread>>>();
    fb_out<<<S_, D_, 0, cudaStreamPerThread>>>(x, gw, wo, wd, (__nv_bfloat16*)d_out);
    return;
  }
  Maps mp;
  { cuuint64_t d[2] = {D_, S_}, s[1] = {D_ * 2}; cuuint32_t b[2] = {64, 128}; encode(fn, &mp.x, x, 2, d, s, b, CU_TENSOR_MAP_SWIZZLE_128B); }
  { cuuint64_t d[2] = {3 * D_, D_}, s[1] = {3 * D_ * 2}; cuuint32_t b[2] = {64, 32}; encode(fn, &mp.qkv, wqkv, 2, d, s, b, CU_TENSOR_MAP_SWIZZLE_128B);
    cuuint32_t b32[2] = {32, 32}; encode(fn, &mp.q32, wqkv, 2, d, s, b32, CU_TENSOR_MAP_SWIZZLE_64B); }
  { cuuint64_t d[2] = {F_, D_}, s[1] = {F_ * 2}; cuuint32_t b[2] = {64, 32};
    encode(fn, &mp.g1, wg, 2, d, s, b, CU_TENSOR_MAP_SWIZZLE_128B); encode(fn, &mp.u1, wu, 2, d, s, b, CU_TENSOR_MAP_SWIZZLE_128B); }
  { cuuint64_t d[3] = {32, D_, F_ / 32}, s[2] = {F_ * 2, 64}; cuuint32_t b3[3] = {32, 32, 3};
    encode(fn, &mp.g3, wg, 3, d, s, b3, CU_TENSOR_MAP_SWIZZLE_64B); encode(fn, &mp.u3, wu, 3, d, s, b3, CU_TENSOR_MAP_SWIZZLE_64B); }
  { cuuint64_t d[2] = {D_, F_}, s[1] = {D_ * 2}; cuuint32_t b64[2] = {64, 64}, b48[2] = {64, 48};
    encode(fn, &mp.wd64, wd, 2, d, s, b64, CU_TENSOR_MAP_SWIZZLE_128B);
    encode(fn, &mp.wd48, wd, 2, d, s, b48, CU_TENSOR_MAP_SWIZZLE_128B); }
  { cuuint64_t d[2] = {D_, D_}, s[1] = {D_ * 2}; cuuint32_t b[2] = {64, 32}; encode(fn, &mp.wo, wo, 2, d, s, b, CU_TENSOR_MAP_SWIZZLE_128B); }
  { cuuint64_t d[2] = {D_, S_}, s[1] = {D_ * 2}; cuuint32_t b[2] = {64, 64}; encode(fn, &mp.out, d_out, 2, d, s, b, CU_TENSOR_MAP_SWIZZLE_128B); }
  fused_kernel<<<NCTA, 384, SMEM_BYTES, cudaStreamPerThread>>>(mp, wqkv, wo, wg, wu, wd, gw, x, (__nv_bfloat16*)d_out);
}
```
